```python
import torch

def _softmax(x, axis=-1):
    return torch.softmax(x, dim=axis)
def _gelu(x):
    return torch.nn.functional.gelu(x, approximate="tanh")
def _silu(x):
    return torch.nn.functional.silu(x)
def _sigmoid(x):
    return torch.sigmoid(x)
def _layernorm(x, axis=-1, eps=1e-5):
    m = x.mean(dim=axis, keepdim=True)
    v = x.var(dim=axis, keepdim=True, unbiased=False)
    return (x - m) / torch.sqrt(v + eps)
def _scatter_add(tgt, idx, src, axis=0):
    return tgt.clone().index_add_(axis, idx, src)
def _segment_sum(src, seg, n):
    out = torch.zeros((n,) + src.shape[1:], dtype=src.dtype)
    return out.index_add_(0, seg, src)
def _pad(x, pw):
    flat = tuple(v for pair in reversed(pw) for v in pair)
    return torch.nn.functional.pad(x, flat)

kernel_name = 'standalone__low_rank_proj_linformer__decode'

def setup_inputs():

    _w = (lambda a: (lambda t: t.to(torch.bfloat16) if t.is_floating_point() else t)(torch.as_tensor(a)))
    B, H, Sq, Skv, Dh, R = 2, 32, 1, 16384, 128, 16
    return {
        "q": _w((lambda *s: torch.randn(*s, dtype=torch.bfloat16) * 0.8)(B, H, Sq, Dh)),
        "k": _w((lambda *s: torch.randn(*s, dtype=torch.bfloat16) * 0.8)(B, H, Skv, Dh)),
        "v": _w((lambda *s: torch.randn(*s, dtype=torch.bfloat16) * 0.05)(B, H, Skv, Dh)),
        "e_proj": _w((lambda *s: torch.randn(*s, dtype=torch.bfloat16) * 0.8)(R, Skv) * (Skv ** -0.5)),
        "f_proj": _w((lambda *s: torch.randn(*s, dtype=torch.bfloat16) * 0.05)(R, Skv) * (Skv ** -0.5)),
    }

def reference(q, k, v, e_proj, f_proj):
    B, H, Sq, Dh = q.shape
    kp = torch.einsum("rn,bhnd->bhrd", e_proj, k)
    vp = torch.einsum("rn,bhnd->bhrd", f_proj, v)
    scores = torch.einsum("bhqd,bhrd->bhqr", q, kp) * (Dh ** -0.5)
    p = _softmax(scores, axis=-1)
    o = torch.einsum("bhqr,bhrd->bhqd", p, vp)
    return o
```

```cpp
#include <cuda_runtime.h>
#include <cuda_bf16.h>
#include <cuda.h>
#include <stdint.h>

namespace lin {

constexpr int BH = 64, SKV = 16384, DH = 128, R = 16;
constexpr int ROWS = 128;
constexpr int KV_BYTES = ROWS * DH * 2;
constexpr int P_BYTES = R * ROWS * 2;
constexpr int STAGE_BYTES = KV_BYTES + P_BYTES;
constexpr int STAGES = 6;
constexpr int TILES = SKV / ROWS / 2;
constexpr int NCW = 4;
constexpr int THREADS = (NCW + 1) * 32;
constexpr int SOFTMAX_AT = TILES + 16;

constexpr int OFF_KP = STAGES * STAGE_BYTES;
constexpr int OFF_O = OFF_KP + R * DH * 4;
constexpr int OFF_SC = OFF_O + DH * 4;
constexpr int OFF_BAR = OFF_SC + NCW * R * 4;
constexpr int SMEM_BYTES = OFF_BAR + 16 * 8 + 1024;

struct Maps { CUtensorMap k, v, e, f; };

__device__ __forceinline__ uint32_t smem_u32(const void* p) { return (uint32_t)__cvta_generic_to_shared(p); }
__device__ __forceinline__ void mbar_init(uint32_t bar, uint32_t cnt) {
    asm volatile("mbarrier.init.shared::cta.b64 [%0], %1;" :: "r"(bar), "r"(cnt) : "memory");
}
__device__ __forceinline__ void mbar_expect_tx(uint32_t bar, uint32_t bytes) {
    asm volatile("mbarrier.arrive.expect_tx.shared::cta.b64 _, [%0], %1;" :: "r"(bar), "r"(bytes) : "memory");
}
__device__ __forceinline__ void mbar_arrive(uint32_t bar) {
    asm volatile("mbarrier.arrive.shared::cta.b64 _, [%0];" :: "r"(bar) : "memory");
}
__device__ __forceinline__ void mbar_wait(uint32_t bar, uint32_t parity) {
    uint32_t ok;
    int spins = 0;
    do {
        asm volatile("{\n.reg .pred p;\nmbarrier.try_wait.parity.shared::cta.b64 p, [%1], %2;\nselp.u32 %0, 1, 0, p;\n}"
                     : "=r"(ok) : "r"(bar), "r"(parity) : "memory");
        if (++spins > (1 << 24)) __trap();
    } while (!ok);
}
__device__ __forceinline__ void mbar_wait_cluster(uint32_t bar, uint32_t parity) {
    uint32_t ok;
    int spins = 0;
    do {
        asm volatile("{\n.reg .pred p;\nmbarrier.try_wait.parity.acquire.cluster.shared::cta.b64 p, [%1], %2;\nselp.u32 %0, 1, 0, p;\n}"
                     : "=r"(ok) : "r"(bar), "r"(parity) : "memory");
        if (++spins > (1 << 24)) __trap();
    } while (!ok);
}
__device__ __forceinline__ void tma3d(uint32_t dst, const CUtensorMap* m, int c0, int c1, int c2, uint32_t bar) {
    asm volatile("cp.async.bulk.tensor.3d.shared::cluster.global.mbarrier::complete_tx::bytes [%0], [%1, {%3, %4, %5}], [%2];"
                 :: "r"(dst), "l"(m), "r"(bar), "r"(c0), "r"(c1), "r"(c2) : "memory");
}
__device__ __forceinline__ void tma3d_hint(uint32_t dst, const CUtensorMap* m, int c0, int c1, int c2, uint32_t bar, uint64_t pol) {
    asm volatile("cp.async.bulk.tensor.3d.shared::cluster.global.mbarrier::complete_tx::bytes.L2::cache_hint [%0], [%1, {%3, %4, %5}], [%2], %6;"
                 :: "r"(dst), "l"(m), "r"(bar), "r"(c0), "r"(c1), "r"(c2), "l"(pol) : "memory");
}
__device__ __forceinline__ void ldsm4(uint32_t (&r)[4], uint32_t addr) {
    asm volatile("ldmatrix.sync.aligned.m8n8.x4.shared.b16 {%0,%1,%2,%3}, [%4];"
                 : "=r"(r[0]), "=r"(r[1]), "=r"(r[2]), "=r"(r[3]) : "r"(addr) : "memory");
}
__device__ __forceinline__ void ldsm4t(uint32_t (&r)[4], uint32_t addr) {
    asm volatile("ldmatrix.sync.aligned.m8n8.x4.trans.shared.b16 {%0,%1,%2,%3}, [%4];"
                 : "=r"(r[0]), "=r"(r[1]), "=r"(r[2]), "=r"(r[3]) : "r"(addr) : "memory");
}
__device__ __forceinline__ void mma16816(float (&c)[4], const uint32_t (&a)[4], uint32_t b0, uint32_t b1) {
    asm volatile("mma.sync.aligned.m16n8k16.row.col.f32.bf16.bf16.f32 {%0,%1,%2,%3}, {%4,%5,%6,%7}, {%8,%9}, {%0,%1,%2,%3};"
                 : "+f"(c[0]), "+f"(c[1]), "+f"(c[2]), "+f"(c[3])
                 : "r"(a[0]), "r"(a[1]), "r"(a[2]), "r"(a[3]), "r"(b0), "r"(b1));
}
__device__ __forceinline__ uint32_t mapa(uint32_t addr, uint32_t rank) {
    uint32_t r;
    asm("mapa.shared::cluster.u32 %0, %1, %2;" : "=r"(r) : "r"(addr), "r"(rank));
    return r;
}
__device__ __forceinline__ float bf16r(float x) { return __bfloat162float(__float2bfloat16_rn(x)); }

__global__ void __cluster_dims__(2, 1, 1) __launch_bounds__(THREADS, 1)
linformer_decode_kernel(const __grid_constant__ Maps maps, const __nv_bfloat16* __restrict__ q,
                        __nv_bfloat16* __restrict__ out) {
    extern __shared__ uint8_t smem_raw[];
    const uint32_t sb = (smem_u32(smem_raw) + 1023u) & ~1023u;
    const uint32_t bar_full = sb + OFF_BAR, bar_empty = bar_full + STAGES * 8;
    const uint32_t bar_kp = bar_empty + STAGES * 8, bar_o = bar_kp + 8;
    const int warp = threadIdx.x >> 5, lane = threadIdx.x & 31;
    const int bh = blockIdx.x >> 1;
    const uint32_t rank = blockIdx.x & 1;

    if (warp == 0) {
        if (lane == 0) {
            asm volatile("prefetch.tensormap [%0];" :: "l"(&maps.k) : "memory");
            asm volatile("prefetch.tensormap [%0];" :: "l"(&maps.e) : "memory");
#pragma unroll
            for (int s = 0; s < STAGES; s++) { mbar_init(bar_full + s * 8, 1); mbar_init(bar_empty + s * 8, NCW); }
            mbar_init(bar_kp, 1);
            mbar_init(bar_o, 1);
            mbar_expect_tx(bar_kp, R * DH * 4);
            mbar_expect_tx(bar_o, DH * 4);
            asm volatile("fence.mbarrier_init.release.cluster;" ::: "memory");
            asm volatile("fence.proxy.async.shared::cta;" ::: "memory");
        }
        __syncwarp();
        asm volatile("barrier.cluster.arrive.release.aligned;" ::: "memory");
        if (lane == 0) {
            uint64_t pol;
            asm volatile("createpolicy.fractional.L2::evict_first.b64 %0, 1.0;" : "=l"(pol));
            int s = 0;
            uint32_t ph = 1;
            for (int i = 0; i < 2 * TILES; i++) {
                const bool isv = i >= TILES;
                const int t = 2 * (i & (TILES - 1)) + rank;
                if (i >= STAGES) mbar_wait(bar_empty + s * 8, ph);
                const uint32_t dst = sb + s * STAGE_BYTES, bar = bar_full + s * 8;
                mbar_expect_tx(bar, STAGE_BYTES);
                tma3d_hint(dst, isv ? &maps.v : &maps.k, 0, 0, bh * SKV + t * ROWS, bar, pol);
                tma3d(dst + KV_BYTES, isv ? &maps.f : &maps.e, 0, 0, t * (ROWS / 64), bar);
                if (i == STAGES - 1) {
                    asm volatile("prefetch.tensormap [%0];" :: "l"(&maps.v) : "memory");
                    asm volatile("prefetch.tensormap [%0];" :: "l"(&maps.f) : "memory");
                }
                if (++s == STAGES) { s = 0; ph ^= 1; }
            }
        }
        return;
    }

    asm volatile("barrier.cluster.arrive.release.aligned;" ::: "memory");
    const int w = warp - 1;
    const int g = lane >> 2, t4 = lane & 3;
    float qv[4][2];
#pragma unroll
    for (int j = 0; j < 4; j++) {
        const __nv_bfloat162 x = *reinterpret_cast<const __nv_bfloat162*>(q + bh * DH + w * 32 + j * 8 + t4 * 2);
        qv[j][0] = __low2float(x);
        qv[j][1] = __high2float(x);
    }
    const int mi = lane >> 3, li = lane & 7;
    const int half = w >> 1;
    const uint32_t xr = ((li & 3) << 1) | half;
    const uint32_t b_row = ((mi & 1) * 8 + li) * 256 + half * 128;
    const uint32_t b_off0 = b_row + ((((w & 1) * 4 + (mi >> 1)) ^ xr) << 4);
    const uint32_t b_off1 = b_off0 ^ 32u;
    const uint32_t a_off = KV_BYTES + ((mi & 1) * 8 + li) * 128 + (((mi >> 1) ^ li) << 4);

    float acc[4][4], kp[4][4];
    float p0 = 0.f, p1 = 0.f;
#pragma unroll
    for (int j = 0; j < 4; j++) { acc[j][0] = acc[j][1] = acc[j][2] = acc[j][3] = 0.f; }

    asm volatile("barrier.cluster.wait.acquire.aligned;" ::: "memory");

    int s = 0;
    uint32_t ph = 0;
    for (int i = 0; i < 2 * TILES; i++) {
        const uint32_t st = sb + s * STAGE_BYTES;
        mbar_wait(bar_full + s * 8, ph);
#pragma unroll
        for (int ks = 0; ks < ROWS / 16; ks++) {
            uint32_t a[4], b0[4], b1[4];
            ldsm4(a, st + ((a_off + (ks >> 2) * 2048) ^ ((ks & 3) << 5)));
            ldsm4t(b0, st + b_off0 + ks * 4096);
            ldsm4t(b1, st + b_off1 + ks * 4096);
            mma16816(acc[0], a, b0[0], b0[1]);
            mma16816(acc[1], a, b0[2], b0[3]);
            mma16816(acc[2], a, b1[0], b1[1]);
            mma16816(acc[3], a, b1[2], b1[3]);
        }
        __syncwarp();
        if (lane == 0) mbar_arrive(bar_empty + s * 8);
        if (++s == STAGES) { s = 0; ph ^= 1; }

        if (i == TILES - 1) {
            const uint32_t dst = mapa(sb + OFF_KP + (w * 32 + lane) * 16, rank ^ 1);
            const uint32_t rbar = mapa(bar_kp, rank ^ 1);
#pragma unroll
            for (int j = 0; j < 4; j++) {
                asm volatile("st.async.weak.shared::cluster.mbarrier::complete_tx::bytes.v4.f32 [%0], {%1,%2,%3,%4}, [%5];"
                             :: "r"(dst + j * 2048), "f"(acc[j][0]), "f"(acc[j][1]), "f"(acc[j][2]), "f"(acc[j][3]), "r"(rbar) : "memory");
#pragma unroll
                for (int e = 0; e < 4; e++) { kp[j][e] = acc[j][e]; acc[j][e] = 0.f; }
            }
        } else if (i == SOFTMAX_AT) {
            mbar_wait_cluster(bar_kp, 0);
            float s0 = 0.f, s1 = 0.f;
#pragma unroll
            for (int j = 0; j < 4; j++) {
                float4 o;
                asm volatile("ld.shared.v4.f32 {%0,%1,%2,%3}, [%4];" : "=f"(o.x), "=f"(o.y), "=f"(o.z), "=f"(o.w)
                             : "r"(sb + OFF_KP + (w * 32 + lane) * 16 + j * 2048) : "memory");
                s0 += bf16r(kp[j][0] + o.x) * qv[j][0] + bf16r(kp[j][1] + o.y) * qv[j][1];
                s1 += bf16r(kp[j][2] + o.z) * qv[j][0] + bf16r(kp[j][3] + o.w) * qv[j][1];
            }
            s0 += __shfl_xor_sync(0xffffffffu, s0, 1);
            s1 += __shfl_xor_sync(0xffffffffu, s1, 1);
            s0 += __shfl_xor_sync(0xffffffffu, s0, 2);
            s1 += __shfl_xor_sync(0xffffffffu, s1, 2);
            if (t4 == 0) {
                asm volatile("st.shared.f32 [%0], %1;" :: "r"(sb + OFF_SC + (w * R + g) * 4), "f"(s0) : "memory");
                asm volatile("st.shared.f32 [%0], %1;" :: "r"(sb + OFF_SC + (w * R + g + 8) * 4), "f"(s1) : "memory");
            }
            asm volatile("bar.sync 1, %0;" :: "n"(NCW * 32) : "memory");
            float sc = 0.f;
#pragma unroll
            for (int ww = 0; ww < NCW; ww++) {
                float x;
                asm volatile("ld.shared.f32 %0, [%1];" : "=f"(x) : "r"(sb + OFF_SC + (ww * R + (lane & 15)) * 4) : "memory");
                sc += x;
            }
            sc = bf16r(bf16r(sc) * 0.08838834764831845f);
            float mx = sc;
#pragma unroll
            for (int o = 1; o < 16; o <<= 1) mx = fmaxf(mx, __shfl_xor_sync(0xffffffffu, mx, o));
            const float ex = expf(sc - mx);
            float sum = ex;
#pragma unroll
            for (int o = 1; o < 16; o <<= 1) sum += __shfl_xor_sync(0xffffffffu, sum, o);
            const float p = bf16r(ex / sum);
            p0 = __shfl_sync(0xffffffffu, p, g);
            p1 = __shfl_sync(0xffffffffu, p, g + 8);
        }
    }

    float v[8];
#pragma unroll
    for (int j = 0; j < 4; j++) {
        v[2 * j] = p0 * acc[j][0] + p1 * acc[j][2];
        v[2 * j + 1] = p0 * acc[j][1] + p1 * acc[j][3];
    }
    {
        const bool hi = lane & 16;
#pragma unroll
        for (int e = 0; e < 4; e++) {
            const float send = hi ? v[e] : v[e + 4], keep = hi ? v[e + 4] : v[e];
            v[e] = keep + __shfl_xor_sync(0xffffffffu, send, 16);
        }
    }
    {
        const bool hi = lane & 8;
#pragma unroll
        for (int e = 0; e < 2; e++) {
            const float send = hi ? v[e] : v[e + 2], keep = hi ? v[e + 2] : v[e];
            v[e] = keep + __shfl_xor_sync(0xffffffffu, send, 8);
        }
    }
    {
        const bool hi = lane & 4;
        const float send = hi ? v[0] : v[1], keep = hi ? v[1] : v[0];
        v[0] = keep + __shfl_xor_sync(0xffffffffu, send, 4);
    }
    const uint32_t slot = sb + OFF_O + (w * 32 + lane) * 4;
    if (rank == 1) {
        asm volatile("st.async.weak.shared::cluster.mbarrier::complete_tx::bytes.f32 [%0], %1, [%2];"
                     :: "r"(mapa(slot, 0)), "f"(v[0]), "r"(mapa(bar_o, 0)) : "memory");
    } else {
        mbar_wait_cluster(bar_o, 0);
        float x;
        asm volatile("ld.shared.f32 %0, [%1];" : "=f"(x) : "r"(slot) : "memory");
        out[bh * DH + w * 32 + 8 * (g >> 1) + 2 * t4 + (g & 1)] = __float2bfloat16_rn(v[0] + x);
    }
}

typedef CUresult (*EncodeFn)(CUtensorMap*, CUtensorMapDataType, cuuint32_t, void*, const cuuint64_t*, const cuuint64_t*,
                             const cuuint32_t*, const cuuint32_t*, CUtensorMapInterleave, CUtensorMapSwizzle,
                             CUtensorMapL2promotion, CUtensorMapFloatOOBfill);

static void encode3d(EncodeFn enc, CUtensorMap* m, void* p, cuuint64_t d1, cuuint64_t d2, cuuint64_t s1, cuuint64_t s2,
                     cuuint32_t b1, cuuint32_t b2) {
    const cuuint64_t dims[3] = {64, d1, d2};
    const cuuint64_t strides[2] = {s1, s2};
    const cuuint32_t box[3] = {64, b1, b2};
    const cuuint32_t es[3] = {1, 1, 1};
    enc(m, CU_TENSOR_MAP_DATA_TYPE_BFLOAT16, 3, p, dims, strides, box, es, CU_TENSOR_MAP_INTERLEAVE_NONE,
        CU_TENSOR_MAP_SWIZZLE_128B, CU_TENSOR_MAP_L2_PROMOTION_NONE, CU_TENSOR_MAP_FLOAT_OOB_FILL_NONE);
}

}

extern "C" void kernel_launch(void* const* d_in, const int* in_sizes, int n_in, void* d_out, int out_size) {
    using namespace lin;
    (void)in_sizes; (void)n_in; (void)out_size;
    static EncodeFn enc = nullptr;
    if (!enc) {
        cudaDriverEntryPointQueryResult qr;
        cudaGetDriverEntryPoint("cuTensorMapEncodeTiled", (void**)&enc, cudaEnableDefault, &qr);
        cudaFuncSetAttribute(linformer_decode_kernel, cudaFuncAttributeMaxDynamicSharedMemorySize, SMEM_BYTES);
    }
    Maps maps;
    encode3d(enc, &maps.k, d_in[1], 2, (cuuint64_t)BH * SKV, 128, 256, 2, ROWS);
    encode3d(enc, &maps.v, d_in[2], 2, (cuuint64_t)BH * SKV, 128, 256, 2, ROWS);
    encode3d(enc, &maps.e, d_in[3], R, SKV / 64, SKV * 2, 128, R, ROWS / 64);
    encode3d(enc, &maps.f, d_in[4], R, SKV / 64, SKV * 2, 128, R, ROWS / 64);
    linformer_decode_kernel<<<2 * BH, THREADS, SMEM_BYTES, cudaStreamPerThread>>>(
        maps, (const __nv_bfloat16*)d_in[0], (__nv_bfloat16*)d_out);
}
```

```cpp
#include <cuda_runtime.h>
#include <cuda_bf16.h>
#include <cuda.h>
#include <stdint.h>

namespace lin {

constexpr int BH = 64, SKV = 16384, DH = 128, R = 16;
constexpr int ROWS = 128;
constexpr int KV_BYTES = ROWS * DH * 2;
constexpr int P_BYTES = R * ROWS * 2;
constexpr int STAGE_BYTES = KV_BYTES + P_BYTES;
constexpr int STAGES = 6;
constexpr int NCW = 8;
constexpr int THREADS = (NCW + 1) * 32;
constexpr int KT = SKV / ROWS / 2;
constexpr int NT = 2 * KT;
constexpr int GRID = 2 * BH;
constexpr int NF = 2;
constexpr uint32_t SEG_END = KT | (KT + 16) << 8 | (KT + 32) << 16 | (NT - NF) << 24;
constexpr int W_ISSUE = KT + 16 + STAGES;
constexpr uint32_t TAPER = 0x134;
constexpr uint32_t PACE_STEP = 1296, PACE_START = 5600;
static_assert(STAGES - (TAPER & 15) >= NF, "no request may depend on the release of a folded tile");

constexpr int OFF_KP = STAGES * STAGE_BYTES;
constexpr int OFF_FL = OFF_KP;
constexpr int OFF_OL = ((NT - 1) % STAGES) * STAGE_BYTES + KV_BYTES;
constexpr int OFF_OR = OFF_KP + R * DH * 4;
constexpr int OFF_SC = OFF_OR + 4 * DH * 4;
constexpr int OFF_FULL = OFF_SC + NCW * R * 4;
constexpr int OFF_EMPTY = OFF_FULL + STAGES * 8;
constexpr int OFF_BKP = OFF_EMPTY + STAGES * 8;
constexpr int OFF_BO = OFF_BKP + 8;
constexpr int OFF_BFL = OFF_BO + 8;
constexpr int OFF_BTURN = OFF_BFL + 8;
constexpr int OFF_BQ = OFF_BTURN + 8;
constexpr int OFF_TURN = OFF_BQ + 4 * 8;
constexpr int SMEM_BYTES = OFF_TURN + 8;
static_assert(SMEM_BYTES <= 232448, "smem");

struct Maps { CUtensorMap k, e, v, f, vq; };

__device__ __forceinline__ uint32_t smem_u32(const void* p) { return (uint32_t)__cvta_generic_to_shared(p); }
__device__ __forceinline__ void mbar_init(uint32_t bar, uint32_t cnt) {
    asm volatile("mbarrier.init.shared::cta.b64 [%0], %1;" :: "r"(bar), "r"(cnt) : "memory");
}
__device__ __forceinline__ void mbar_expect_tx(uint32_t bar, uint32_t bytes) {
    asm volatile("mbarrier.arrive.expect_tx.shared::cta.b64 _, [%0], %1;" :: "r"(bar), "r"(bytes) : "memory");
}
__device__ __forceinline__ void mbar_arrive_if(uint32_t bar, uint32_t cond) {
    asm volatile("{\n.reg .pred p;\nsetp.ne.u32 p, %1, 0;\n@p mbarrier.arrive.shared::cta.b64 _, [%0];\n}" :: "r"(bar), "r"(cond) : "memory");
}
__device__ __forceinline__ void mbar_wait(uint32_t bar, uint32_t parity) {
    asm volatile("{\n.reg .pred p;\n.reg .u32 c;\nmov.u32 c, 0;\n"
                 "W_LOOP:\nmbarrier.try_wait.parity.shared::cta.b64 p, [%0], %1;\n@p bra W_DONE;\n"
                 "add.u32 c, c, 1;\nsetp.lt.u32 p, c, 2097152;\n@p bra W_LOOP;\ntrap;\nW_DONE:\n}"
                 :: "r"(bar), "r"(parity) : "memory");
}
__device__ __forceinline__ void mbar_wait_cluster(uint32_t bar, uint32_t parity) {
    asm volatile("{\n.reg .pred p;\n.reg .u32 c;\nmov.u32 c, 0;\n"
                 "W_LOOP:\nmbarrier.try_wait.parity.relaxed.cluster.shared::cta.b64 p, [%0], %1;\n@p bra W_DONE;\n"
                 "add.u32 c, c, 1;\nsetp.lt.u32 p, c, 2097152;\n@p bra W_LOOP;\ntrap;\nW_DONE:\n}\n"
                 "fence.acquire.sync_restrict::shared::cluster.cluster;"
                 :: "r"(bar), "r"(parity) : "memory");
}
__device__ __forceinline__ bool elect_one() {
    uint32_t p;
    asm volatile("{\n.reg .pred p;\nelect.sync _|p, 0xffffffff;\nselp.u32 %0, 1, 0, p;\n}" : "=r"(p));
    return p;
}
__device__ __forceinline__ void tma3d(uint32_t dst, const CUtensorMap* m, int c2, uint32_t bar) {
    asm volatile("cp.async.bulk.tensor.3d.shared::cluster.global.mbarrier::complete_tx::bytes [%0], [%1, {0, 0, %3}], [%2];"
                 :: "r"(dst), "l"(m), "r"(bar), "r"(c2) : "memory");
}
__device__ __forceinline__ void tma3d_hint(uint32_t dst, const CUtensorMap* m, int c2, uint32_t bar, uint64_t pol) {
    asm volatile("cp.async.bulk.tensor.3d.shared::cluster.global.mbarrier::complete_tx::bytes.L2::cache_hint [%0], [%1, {0, 0, %3}], [%2], %4;"
                 :: "r"(dst), "l"(m), "r"(bar), "r"(c2), "l"(pol) : "memory");
}
__device__ __forceinline__ void ldsm4(uint32_t (&r)[4], uint32_t addr) {
    asm volatile("ldmatrix.sync.aligned.m8n8.x4.shared.b16 {%0,%1,%2,%3}, [%4];"
                 : "=r"(r[0]), "=r"(r[1]), "=r"(r[2]), "=r"(r[3]) : "r"(addr) : "memory");
}
__device__ __forceinline__ void ldsm4t(uint32_t (&r)[4], uint32_t addr) {
    asm volatile("ldmatrix.sync.aligned.m8n8.x4.trans.shared.b16 {%0,%1,%2,%3}, [%4];"
                 : "=r"(r[0]), "=r"(r[1]), "=r"(r[2]), "=r"(r[3]) : "r"(addr) : "memory");
}
__device__ __forceinline__ void mma16816(float (&c)[4], const uint32_t (&a)[4], uint32_t b0, uint32_t b1) {
    asm volatile("mma.sync.aligned.m16n8k16.row.col.f32.bf16.bf16.f32 {%0,%1,%2,%3}, {%4,%5,%6,%7}, {%8,%9}, {%0,%1,%2,%3};"
                 : "+f"(c[0]), "+f"(c[1]), "+f"(c[2]), "+f"(c[3])
                 : "r"(a[0]), "r"(a[1]), "r"(a[2]), "r"(a[3]), "r"(b0), "r"(b1));
}
__device__ __forceinline__ uint32_t mapa(uint32_t addr, uint32_t rank) {
    uint32_t r;
    asm("mapa.shared::cluster.u32 %0, %1, %2;" : "=r"(r) : "r"(addr), "r"(rank));
    return r;
}
__device__ __forceinline__ uint32_t pack_bf16(float lo, float hi) {
    uint32_t r;
    asm("cvt.rn.bf16x2.f32 %0, %1, %2;" : "=r"(r) : "f"(hi), "f"(lo));
    return r;
}
__device__ __forceinline__ uint32_t now_ns() {
    uint32_t t;
    asm volatile("mov.u32 %0, %globaltimer_lo;" : "=r"(t));
    return t;
}
__device__ __forceinline__ float bf16r(float x) { return __bfloat162float(__float2bfloat16_rn(x)); }
__device__ __forceinline__ uint32_t pin(uint32_t x) { return __shfl_sync(0xffffffffu, x, threadIdx.x & 31); }
__device__ __forceinline__ uint32_t pin_uniform(uint32_t x) { return __shfl_sync(0xffffffffu, x, 0); }

__device__ __forceinline__ void issue_stage(uint32_t sb, int s, const CUtensorMap* mx, int row, uint64_t pol) {
    const uint32_t dst = sb + s * STAGE_BYTES, bar = sb + OFF_FULL + s * 8;
    mbar_expect_tx(bar, STAGE_BYTES);
    tma3d_hint(dst, mx, row, bar, pol);
    tma3d(dst + KV_BYTES, mx + 1, (row & (SKV - 1)) >> 6, bar);
}

__global__ void __cluster_dims__(2, 1, 1) __launch_bounds__(THREADS, 1)
linformer_decode_kernel(const __grid_constant__ Maps maps, const __nv_bfloat16* __restrict__ q,
                        __nv_bfloat16* __restrict__ out, const uint32_t pace_start, const uint32_t pace_step) {
    extern __shared__ __align__(1024) uint8_t smem_raw[];
    asm volatile("prefetch.tensormap [%0];" :: "l"(&maps.k) : "memory");
    uint32_t sb = smem_u32(smem_raw);
    const int bh = blockIdx.x >> 1;
    const uint32_t rank = blockIdx.x & 1;
    uint64_t pol;
    asm volatile("createpolicy.fractional.L2::evict_first.b64 %0, 1.0;" : "=l"(pol));
    if (threadIdx.x == 0) {
        const int row0 = bh * SKV + rank * ROWS;
        mbar_init(sb + OFF_FULL, 1);
        issue_stage(sb, 0, &maps.k, row0, pol);
#pragma unroll 1
        for (int s = 1; s < STAGES; s++) {
            mbar_init(sb + OFF_FULL + s * 8, 1);
            issue_stage(sb, s, &maps.k, row0 + s * 2 * ROWS, pol);
        }
#pragma unroll
        for (int s = 0; s < STAGES; s++) mbar_init(sb + OFF_EMPTY + s * 8, NCW);
        mbar_init(sb + OFF_BKP, 1);
        mbar_init(sb + OFF_BO, 1 + NCW);
        mbar_init(sb + OFF_BFL, 1);
        mbar_init(sb + OFF_BTURN, 1);
#pragma unroll
        for (int u = 0; u < 4; u++) {
            mbar_init(sb + OFF_BQ + u * 8, 1);
            mbar_expect_tx(sb + OFF_BQ + u * 8, KV_BYTES / 4);
        }
        asm volatile("st.shared.u32 [%0], %1;\nfence.release.sync_restrict::shared::cta.cluster;" :: "r"(sb + OFF_TURN), "r"(0) : "memory");
        mbar_expect_tx(sb + OFF_BKP, R * DH * 4);
        mbar_expect_tx(sb + OFF_BO, 4 * DH * 4);
        asm volatile("fence.mbarrier_init.release.cluster;" ::: "memory");
        asm volatile("prefetch.tensormap [%0];" :: "l"(&maps.v) : "memory");
        asm volatile("prefetch.tensormap [%0];" :: "l"(&maps.f) : "memory");
        asm volatile("prefetch.tensormap [%0];" :: "l"(&maps.vq) : "memory");
        if (sb & 1023u) __trap();
    }
    const int warp = pin_uniform(threadIdx.x >> 5), lane = threadIdx.x & 31;
    if (warp == 0) {
        const bool leader = elect_one();
        __syncwarp();
        asm volatile("barrier.cluster.arrive.relaxed.aligned;" ::: "memory");
        if (leader) {
            uint32_t due = now_ns() + pace_start;
            int s = 0, j = 0, js = 0;
            uint32_t jph = 0;
#pragma unroll 1
            for (int i = STAGES; i < NT; i++) {
                const int rem = NT - 1 - i;
                const int win = rem < 8 ? STAGES - (int)((TAPER >> (4 * rem)) & 15) : STAGES;
#pragma unroll 1
                for (; j <= i - win; j++) {
                    mbar_wait(sb + OFF_EMPTY + js * 8, jph);
                    if (++js == STAGES) { js = 0; jph ^= 1; }
                }
                for (int spins = 0; (int)(now_ns() - due) < 0 && spins < (1 << 16); spins++) __nanosleep(20);
                due += pace_step;
                const int row = bh * SKV + (2 * (i & (KT - 1)) + rank) * ROWS;
                if (i == W_ISSUE) {
                    mbar_expect_tx(sb + OFF_BFL, NF * P_BYTES);
#pragma unroll
                    for (int u = 0; u < NF; u++)
                        tma3d(sb + OFF_FL + u * P_BYTES, &maps.f, (2 * (KT - NF + u) + rank) * (ROWS / 64), sb + OFF_BFL);
                }
                if (rem >= NF) {
                    issue_stage(sb, s, i >= KT ? &maps.v : &maps.k, row, pol);
                } else if (rem) {
                    mbar_expect_tx(sb + OFF_FULL + s * 8, KV_BYTES);
                    tma3d_hint(sb + s * STAGE_BYTES, &maps.v, row, sb + OFF_FULL + s * 8, pol);
                } else {
#pragma unroll
                    for (int u = 0; u < 4; u++)
                        tma3d_hint(sb + s * STAGE_BYTES + u * (KV_BYTES / 4), &maps.vq, row + u * (ROWS / 4), sb + OFF_BQ + u * 8, pol);
                }
                if (++s == STAGES) s = 0;
            }
            uint32_t turn;
            asm volatile("atom.relaxed.cluster.shared::cluster.add.u32 %0, [%1], 1;" : "=r"(turn) : "r"(mapa(sb + OFF_TURN, 0)) : "memory");
            asm volatile("st.shared.u32 [%0], %1;" :: "r"(sb + OFF_TURN + 4), "r"(turn) : "memory");
            mbar_arrive_if(sb + OFF_BTURN, 1);
            for (int spins = 0; rank == 0 && turn == 0; spins++) {
                asm volatile("ld.volatile.shared.u32 %0, [%1];" : "=r"(turn) : "r"(sb + OFF_TURN) : "memory");
                turn >>= 1;
                if (spins > (1 << 22)) __trap();
                __nanosleep(100);
            }
        }
        return;
    }

    asm volatile("barrier.cluster.arrive.relaxed.aligned;" ::: "memory");
    sb = pin_uniform(sb);
    const int w = warp - 1;
    const int cg = w & 1, rg = w >> 1;
    const int g = lane >> 2, t4 = lane & 3;
    const int mi = lane >> 3, li = lane & 7;
    const uint32_t xr = ((li & 3) << 1) | cg;
    const uint32_t x_off = (rg * 32 + (mi >> 1) * 8 + li) * 256 + cg * 128 + ((((mi & 1) ^ (li >> 2)) ^ xr) << 4);
    const uint32_t p_off = KV_BYTES + (rg >> 1) * 2048 + ((mi >> 1) * 8 + li) * 128 + ((((rg & 1) * 4 + (mi & 1)) ^ li) << 4);
    const bool sw = t4 >= 2;
    const uint32_t xo[4] = {pin(x_off), pin(x_off ^ 32u), pin(x_off ^ 64u), pin(x_off ^ 96u)};
    const uint32_t po[2] = {pin(p_off), pin(p_off ^ 32u)};
    const uint32_t lead = elect_one();

    float acc[4][2][4], kp[2][4];
    float pr[4] = {0.f, 0.f, 0.f, 0.f};
#pragma unroll
    for (int j = 0; j < 8; j++) { acc[j >> 1][j & 1][0] = acc[j >> 1][j & 1][1] = acc[j >> 1][j & 1][2] = acc[j >> 1][j & 1][3] = 0.f; }
    const uint32_t o_dst = pin(sb + OFF_OL + (rg * 128 + cg * 32 + lane) * 4);
    const uint32_t o_rdst = pin(mapa(sb + OFF_OR + (rg * 128 + cg * 32 + lane) * 4, rank ^ 1));
    const uint32_t o_rbar = pin(mapa(sb + OFF_BO, rank ^ 1));
    const uint32_t o_src = pin(sb + ((rg & 1) * 64 + cg * 32 + lane) * 4);
    const uint64_t o_addr = (uint64_t)(out + bh * DH + cg * 64 + t4 * 16 + (rg & 1) * 8 + g);
    const uint32_t o_lo = pin((uint32_t)o_addr), o_hi = pin((uint32_t)(o_addr >> 32));
    const uint32_t opq = pin_uniform(blockDim.x);

    uint32_t ph = 0, st = sb, fbar = sb + OFF_FULL;
    struct Half { uint32_t e[4], x[4][4]; };
    auto load = [&](Half& f, int k) {
        ldsm4t(f.x[0], st + xo[0] + k * 4096);
        ldsm4(f.e, st + po[k]);
#pragma unroll
        for (int m = 1; m < 4; m++) ldsm4t(f.x[m], st + xo[m] + k * 4096);
    };
    auto fix = [&](uint32_t (&a)[4], const uint32_t (&x)[4]) {
        a[0] = sw ? x[1] : x[0]; a[1] = sw ? x[0] : x[1]; a[2] = sw ? x[3] : x[2]; a[3] = sw ? x[2] : x[3];
    };
    auto mma = [&](const Half& f) {
#pragma unroll
        for (int m = 0; m < 4; m++) {
            uint32_t a[4];
            fix(a, f.x[m]);
            mma16816(acc[m][0], a, f.e[0], f.e[1]);
            mma16816(acc[m][1], a, f.e[2], f.e[3]);
        }
    };
    auto clear = [&](Half& f) {
#pragma unroll
        for (int z = 0; z < 4; z++) { f.e[z] = 0; f.x[0][z] = f.x[1][z] = f.x[2][z] = f.x[3][z] = 0; }
    };

    Half h0, h1;
    clear(h1);
    asm volatile("barrier.cluster.wait.acquire.aligned;" ::: "memory");
    uint16_t qraw0, qraw1;
    asm volatile("ld.global.nc.u16 %0, [%1];" : "=h"(qraw0) : "l"(q + bh * DH + cg * 64 + rg * 16 + g) : "memory");
    asm volatile("ld.global.nc.u16 %0, [%1];" : "=h"(qraw1) : "l"(q + bh * DH + cg * 64 + rg * 16 + g + 8) : "memory");
    uint32_t wb[NF][2][2] = {};
    int i = 0;
#pragma unroll 1
    for (int seg = 0;; seg++) {
        const int seg_end = (SEG_END >> (8 * seg)) & 255;
#pragma unroll 1
        for (; i < seg_end; i++) {
            const uint32_t rel = lead & (i != KT - 1);
            mbar_wait(fbar, ph);
            load(h0, 0);
            mma(h1);
            load(h1, 1);
            __syncwarp();
            mbar_arrive_if(fbar + STAGES * 8, rel);
            mma(h0);
            st += STAGE_BYTES;
            fbar += 8;
            if (fbar == sb + OFF_EMPTY) { ph ^= 1; st = sb; fbar = sb + OFF_FULL; }
        }
        if (i == NT - NF) break;
        if (seg == 0) {
            mma(h1);
            clear(h1);
            constexpr int SK = (KT - 1) % STAGES;
            const uint32_t scr = sb + SK * STAGE_BYTES + lane * 16;
            asm volatile("bar.sync 1, %0;" :: "n"(NCW * 32) : "memory");
#pragma unroll
            for (int j = 0; j < 8; j++) {
                asm volatile("st.shared.v4.f32 [%0], {%1,%2,%3,%4};" :: "r"(scr + ((rg * 2 + cg) * 8 + j) * 512),
                             "f"(acc[j >> 1][j & 1][0]), "f"(acc[j >> 1][j & 1][1]), "f"(acc[j >> 1][j & 1][2]), "f"(acc[j >> 1][j & 1][3]) : "memory");
                acc[j >> 1][j & 1][0] = acc[j >> 1][j & 1][1] = acc[j >> 1][j & 1][2] = acc[j >> 1][j & 1][3] = 0.f;
            }
            asm volatile("bar.sync 1, %0;" :: "n"(NCW * 32) : "memory");
#pragma unroll
            for (int n = 0; n < 2; n++) {
                kp[n][0] = kp[n][1] = kp[n][2] = kp[n][3] = 0.f;
#pragma unroll
                for (int r2 = 0; r2 < 4; r2++) {
                    float4 o;
                    asm volatile("ld.shared.v4.f32 {%0,%1,%2,%3}, [%4];" : "=f"(o.x), "=f"(o.y), "=f"(o.z), "=f"(o.w)
                                 : "r"(scr + ((r2 * 2 + cg) * 8 + rg * 2 + n) * 512) : "memory");
                    kp[n][0] += o.x; kp[n][1] += o.y; kp[n][2] += o.z; kp[n][3] += o.w;
                }
            }
            asm volatile("fence.proxy.async.shared::cta;" ::: "memory");
            __syncwarp();
            mbar_arrive_if(sb + OFF_EMPTY + SK * 8, lead);
            const uint32_t dst = mapa(sb + OFF_KP + (w * 64 + lane) * 16, rank ^ 1);
            const uint32_t rbar = mapa(sb + OFF_BKP, rank ^ 1);
#pragma unroll
            for (int n = 0; n < 2; n++)
                asm volatile("st.async.weak.shared::cluster.mbarrier::complete_tx::bytes.v4.f32 [%0], {%1,%2,%3,%4}, [%5];"
                             :: "r"(dst + n * 512), "f"(kp[n][0]), "f"(kp[n][1]), "f"(kp[n][2]), "f"(kp[n][3]), "r"(rbar) : "memory");
        } else if (seg == 1) {
            mbar_wait_cluster(sb + OFF_BKP, 0);
            float q0, q1;
            asm volatile("mov.b32 %0, {%2, %1};" : "=f"(q0) : "h"(qraw0), "h"((uint16_t)0) : "memory");
            asm volatile("mov.b32 %0, {%2, %1};" : "=f"(q1) : "h"(qraw1), "h"((uint16_t)0) : "memory");
            float sc4[4];
#pragma unroll
            for (int n = 0; n < 2; n++) {
                float4 o;
                asm volatile("ld.shared.v4.f32 {%0,%1,%2,%3}, [%4];" : "=f"(o.x), "=f"(o.y), "=f"(o.z), "=f"(o.w)
                             : "r"(sb + OFF_KP + (w * 64 + lane) * 16 + n * 512) : "memory");
                sc4[2 * n] = bf16r(kp[n][0] + o.x) * q0 + bf16r(kp[n][2] + o.z) * q1;
                sc4[2 * n + 1] = bf16r(kp[n][1] + o.y) * q0 + bf16r(kp[n][3] + o.w) * q1;
            }
#pragma unroll
            for (int e2 = 0; e2 < 4; e2++) {
                sc4[e2] += __shfl_xor_sync(0xffffffffu, sc4[e2], 4);
                sc4[e2] += __shfl_xor_sync(0xffffffffu, sc4[e2], 8);
                sc4[e2] += __shfl_xor_sync(0xffffffffu, sc4[e2], 16);
            }
            if (g == 0) {
                asm volatile("st.shared.v2.f32 [%0], {%1,%2};" :: "r"(sb + OFF_SC + (w * R + 2 * t4) * 4), "f"(sc4[0]), "f"(sc4[1]) : "memory");
                asm volatile("st.shared.v2.f32 [%0], {%1,%2};" :: "r"(sb + OFF_SC + (w * R + 8 + 2 * t4) * 4), "f"(sc4[2]), "f"(sc4[3]) : "memory");
            }
            asm volatile("bar.sync 1, %0;" :: "n"(NCW * 32) : "memory");
            float sc = 0.f;
#pragma unroll
            for (int ww = 0; ww < NCW; ww++) {
                float x2;
                asm volatile("ld.shared.f32 %0, [%1];" : "=f"(x2) : "r"(sb + OFF_SC + (ww * R + (lane & 15)) * 4) : "memory");
                sc += x2;
            }
            sc = bf16r(bf16r(sc) * 0.08838834764831845f);
            float mx = sc;
#pragma unroll
            for (int o = 1; o < 16; o <<= 1) mx = fmaxf(mx, __shfl_xor_sync(0xffffffffu, mx, o));
            const float ex = expf(sc - mx);
            float sum = ex;
#pragma unroll
            for (int o = 1; o < 16; o <<= 1) sum += __shfl_xor_sync(0xffffffffu, sum, o);
            const float p = bf16r(ex / sum);
            pr[0] = __shfl_sync(0xffffffffu, p, 2 * t4);
            pr[1] = __shfl_sync(0xffffffffu, p, 2 * t4 + 1);
            pr[2] = __shfl_sync(0xffffffffu, p, 2 * t4 + 8);
            pr[3] = __shfl_sync(0xffffffffu, p, 2 * t4 + 9);
        } else {
            mbar_wait(sb + OFF_BFL, 0);
            const uint32_t p01 = pack_bf16(pr[0], pr[1]), p23 = pack_bf16(pr[2], pr[3]);
            const uint32_t pa[4] = {p01, p01, p23, p23};
#pragma unroll
            for (int uk = 0; uk < 2 * NF; uk++) {
                const int u = uk >> 1, k = uk & 1;
                uint32_t fb[4];
                ldsm4t(fb, sb + OFF_FL + u * P_BYTES + (rg >> 1) * 2048 + ((mi & 1) * 8 + li) * 128 + ((((rg & 1) * 4 + k * 2 + (mi >> 1)) ^ li) << 4));
#pragma unroll
                for (int n = 0; n < 2; n++) {
                    float c[4] = {0.f, 0.f, 0.f, 0.f};
                    mma16816(c, pa, fb[2 * n], fb[2 * n + 1]);
                    const uint32_t hi = pack_bf16(c[0], c[1]);
                    const uint32_t lo = pack_bf16(c[0] - __uint_as_float(hi << 16), c[1] - __uint_as_float(hi & 0xffff0000u));
                    wb[u][k][n] = (g & 1) ? lo : hi;
                }
            }
        }
    }

    mma(h1);
    float v[4][2];
#pragma unroll
    for (int m = 0; m < 4; m++)
#pragma unroll
        for (int h = 0; h < 2; h++)
            v[m][h] = (pr[0] * acc[m][0][2 * h] + pr[1] * acc[m][0][2 * h + 1]) + (pr[2] * acc[m][1][2 * h] + pr[3] * acc[m][1][2 * h + 1]);
    {
        const bool odd = lane & 1;
#pragma unroll
        for (int h = 0; h < 2; h++) {
            const float a0 = (sw ? v[2][h] : v[0][h]) + __shfl_xor_sync(0xffffffffu, sw ? v[0][h] : v[2][h], 2);
            const float a1 = (sw ? v[3][h] : v[1][h]) + __shfl_xor_sync(0xffffffffu, sw ? v[1][h] : v[3][h], 2);
            v[0][h] = (odd ? a1 : a0) + __shfl_xor_sync(0xffffffffu, odd ? a0 : a1, 1);
        }
    }
    float dl[2][4] = {{v[0][0], 0.f, v[0][1], 0.f}, {0.f, 0.f, 0.f, 0.f}};
    uint32_t role = 0;
    uint32_t wm[NF][2][4][2];
#pragma unroll
    for (int u = 0; u < NF; u++)
#pragma unroll
        for (int k = 0; k < 2; k++)
#pragma unroll
            for (int m = 0; m < 4; m++) {
                wm[u][k][m][0] = (g >> 1) == m ? wb[u][k][0] : 0u; wm[u][k][m][1] = (g >> 1) == m ? wb[u][k][1] : 0u;
                asm volatile("" : "+r"(wm[u][k][m][0]), "+r"(wm[u][k][m][1]));
            }
#pragma unroll
    for (int u = 0; u < NF; u++) {
        uint32_t xl[4][2][4];
        if (u == NF - 2) {
            mbar_wait(sb + OFF_BTURN, 0);
            uint32_t turn;
            asm volatile("ld.shared.u32 %0, [%1];" : "=r"(turn) : "r"(sb + OFF_TURN + 4) : "memory");
            role = pin_uniform(turn ? (rg < 2 ? 0u : 1u) : 2u);
        }
        if (opq != u) {
            if (u + 1 < NF) mbar_wait(fbar, ph); else mbar_wait(sb + OFF_BQ + rg * 8, 0);
#pragma unroll
            for (int m = 0; m < 4; m++)
#pragma unroll
                for (int k = 0; k < 2; k++) ldsm4t(xl[m][k], st + xo[m] + k * 4096);
        }
        if (u + 1 < NF) {
            st += STAGE_BYTES;
            fbar += 8;
            if (fbar == sb + OFF_EMPTY) { ph ^= 1; st = sb; fbar = sb + OFF_FULL; }
        }
#pragma unroll
        for (int m = 0; m < 4; m++)
#pragma unroll
            for (int k = 0; k < 2; k++) {
                uint32_t a[4];
                asm volatile("" : "+r"(xl[m][k][0]), "+r"(xl[m][k][1]), "+r"(xl[m][k][2]), "+r"(xl[m][k][3]));
                fix(a, xl[m][k]);
                mma16816(dl[k], a, wm[u][k][m][0], wm[u][k][m][1]);
            }
    }
    const float o0 = (dl[0][0] + dl[0][1]) + (dl[1][0] + dl[1][1]), o1 = (dl[0][2] + dl[0][3]) + (dl[1][2] + dl[1][3]);
    if (role == 2) {
        asm volatile("st.async.weak.shared::cluster.mbarrier::complete_tx::bytes.f32 [%0], %1, [%2];"
                     :: "r"(o_rdst), "f"(o0), "r"(o_rbar) : "memory");
        asm volatile("st.async.weak.shared::cluster.mbarrier::complete_tx::bytes.f32 [%0], %1, [%2];"
                     :: "r"(o_rdst + 256), "f"(o1), "r"(o_rbar) : "memory");
    } else {
        asm volatile("st.shared.f32 [%0], %1;" :: "r"(o_dst), "f"(o0) : "memory");
        asm volatile("st.shared.f32 [%0], %1;" :: "r"(o_dst + 256), "f"(o1) : "memory");
        __syncwarp();
        mbar_arrive_if(sb + OFF_BO, lead);
        if (role == 0) {
            mbar_wait_cluster(sb + OFF_BO, 0);
            float y[8];
#pragma unroll
            for (int j = 0; j < 8; j++) asm volatile("ld.shared.f32 %0, [%1];" : "=f"(y[j]) : "r"(o_src + (j < 4 ? OFF_OL : OFF_OR) + (j & 3) * 512) : "memory");
            const __nv_bfloat16 o = __float2bfloat16_rn(((y[0] + y[1]) + (y[2] + y[3])) + ((y[4] + y[5]) + (y[6] + y[7])));
            asm volatile("st.global.u16 [%0], %1;" :: "l"(((uint64_t)o_hi << 32) | o_lo), "h"(__bfloat16_as_ushort(o)) : "memory");
        }
    }
}

typedef CUresult (*EncodeFn)(CUtensorMap*, CUtensorMapDataType, cuuint32_t, void*, const cuuint64_t*, const cuuint64_t*,
                             const cuuint32_t*, const cuuint32_t*, CUtensorMapInterleave, CUtensorMapSwizzle,
                             CUtensorMapL2promotion, CUtensorMapFloatOOBfill);

static void encode3d(EncodeFn enc, CUtensorMap* m, void* p, cuuint64_t d1, cuuint64_t d2, cuuint64_t s1, cuuint64_t s2,
                     cuuint32_t b1, cuuint32_t b2) {
    const cuuint64_t dims[3] = {64, d1, d2};
    const cuuint64_t strides[2] = {s1, s2};
    const cuuint32_t box[3] = {64, b1, b2};
    const cuuint32_t es[3] = {1, 1, 1};
    enc(m, CU_TENSOR_MAP_DATA_TYPE_BFLOAT16, 3, p, dims, strides, box, es, CU_TENSOR_MAP_INTERLEAVE_NONE,
        CU_TENSOR_MAP_SWIZZLE_128B, CU_TENSOR_MAP_L2_PROMOTION_NONE, CU_TENSOR_MAP_FLOAT_OOB_FILL_NONE);
}

}

extern "C" void kernel_launch(void* const* d_in, const int* in_sizes, int n_in, void* d_out, int out_size) {
    using namespace lin;
    (void)in_sizes; (void)n_in; (void)out_size;
    static EncodeFn enc = nullptr;
    static bool paced = false;
    if (!enc) {
        int dev = 0, khz = 0, bits = 0, sms = 0;
        cudaGetDevice(&dev);
        cudaDeviceGetAttribute(&khz, cudaDevAttrMemoryClockRate, dev);
        cudaDeviceGetAttribute(&bits, cudaDevAttrGlobalMemoryBusWidth, dev);
        cudaDeviceGetAttribute(&sms, cudaDevAttrMultiProcessorCount, dev);
        paced = khz == 2619000 && bits == 5120 && sms >= GRID;
        cudaDriverEntryPointQueryResult qr;
        cudaGetDriverEntryPoint("cuTensorMapEncodeTiled", (void**)&enc, cudaEnableDefault, &qr);
        cudaFuncSetAttribute(linformer_decode_kernel, cudaFuncAttributeMaxDynamicSharedMemorySize, SMEM_BYTES);
    }
    Maps maps;
    encode3d(enc, &maps.k, d_in[1], 2, (cuuint64_t)BH * SKV, 128, 256, 2, ROWS);
    encode3d(enc, &maps.v, d_in[2], 2, (cuuint64_t)BH * SKV, 128, 256, 2, ROWS);
    encode3d(enc, &maps.vq, d_in[2], 2, (cuuint64_t)BH * SKV, 128, 256, 2, ROWS / 4);
    encode3d(enc, &maps.e, d_in[3], R, SKV / 64, SKV * 2, 128, R, ROWS / 64);
    encode3d(enc, &maps.f, d_in[4], R, SKV / 64, SKV * 2, 128, R, ROWS / 64);
    linformer_decode_kernel<<<GRID, THREADS, SMEM_BYTES, cudaStreamPerThread>>>(
        maps, (const __nv_bfloat16*)d_in[0], (__nv_bfloat16*)d_out, paced ? PACE_START : 0u, paced ? PACE_STEP : 0u);
}
```
